```python
import torch

def _softmax(x, axis=-1):
    return torch.softmax(x, dim=axis)
def _gelu(x):
    return torch.nn.functional.gelu(x, approximate="tanh")
def _silu(x):
    return torch.nn.functional.silu(x)
def _sigmoid(x):
    return torch.sigmoid(x)
def _layernorm(x, axis=-1, eps=1e-5):
    m = x.mean(dim=axis, keepdim=True)
    v = x.var(dim=axis, keepdim=True, unbiased=False)
    return (x - m) / torch.sqrt(v + eps)
def _scatter_add(tgt, idx, src, axis=0):
    return tgt.clone().index_add_(axis, idx, src)
def _segment_sum(src, seg, n):
    out = torch.zeros((n,) + src.shape[1:], dtype=src.dtype)
    return out.index_add_(0, seg, src)
def _pad(x, pw):
    flat = tuple(v for pair in reversed(pw) for v in pair)
    return torch.nn.functional.pad(x, flat)

kernel_name = 'interleave_layers__spectral_fnet__dense_activation_relu__prompt'

def setup_inputs():

    _w = (lambda a: (lambda t: t.to(torch.bfloat16) if t.is_floating_point() else t)(torch.as_tensor(a)))
    def _A_setup():
        B, S, D = 1, 2048, 576
        ns = torch.arange(S)[:, None] * torch.arange(S)[None, :]
        nd = torch.arange(D)[:, None] * torch.arange(D)[None, :]
        Ws_re = torch.cos(-2.0 * torch.pi * ns / S).to(float)
        Ws_im = torch.sin(-2.0 * torch.pi * ns / S).to(float)
        Wd_re = torch.cos(-2.0 * torch.pi * nd / D).to(float)
        Wd_im = torch.sin(-2.0 * torch.pi * nd / D).to(float)
        return {
            "x": _w((lambda *s: torch.randn(*s, dtype=torch.bfloat16) * 0.05)(B, S, D)),
            "dft_seq_re": _w(Ws_re),
            "dft_seq_im": _w(Ws_im),
            "dft_hid_re": _w(Wd_re),
            "dft_hid_im": _w(Wd_im),
        }
    _A_in = _A_setup()

    def _B_setup():
        B, S, D, Dff = 1, 2048, 576, 4608
        return {
            "x": _w((lambda *s: torch.randn(*s, dtype=torch.bfloat16) * 0.05)(B, S, D)),
            "w1": _w((lambda *s: torch.randn(*s, dtype=torch.bfloat16) * 1.6)(D, Dff)),
            "w2": _w((lambda *s: torch.randn(*s, dtype=torch.bfloat16) * 1.6)(Dff, D)),
        }
    _B_in = _B_setup()

    return {
        "A_x": _A_in["x"],
        "A_dft_seq_re": _A_in["dft_seq_re"],
        "A_dft_seq_im": _A_in["dft_seq_im"],
        "A_dft_hid_re": _A_in["dft_hid_re"],
        "A_dft_hid_im": _A_in["dft_hid_im"],
        "B_x": _B_in["x"],
        "B_w1": _B_in["w1"],
        "B_w2": _B_in["w2"],
    }

def reference(A_x, A_dft_seq_re, A_dft_seq_im, A_dft_hid_re, A_dft_hid_im, B_x, B_w1, B_w2):
    def _A_ref(x, dft_seq_re, dft_seq_im, dft_hid_re, dft_hid_im):
        a = torch.einsum("bsd,ed->bse", x, dft_hid_re)
        b = torch.einsum("bsd,ed->bse", x, dft_hid_im)
        y = torch.einsum("ts,bse->bte", dft_seq_re, a) - torch.einsum("ts,bse->bte", dft_seq_im, b)
        return y

    def _B_ref(x, w1, w2):
        h = torch.einsum("bsd,df->bsf", x, w1)
        zero = torch.zeros_like(h)
        h = torch.maximum(h, zero)
        return torch.einsum("bsf,fd->bsd", h, w2)

    x = A_x
    x = x + _A_ref(_layernorm(x, axis=-1), A_dft_seq_re, A_dft_seq_im, A_dft_hid_re, A_dft_hid_im)
    x = x + _B_ref(_layernorm(x, axis=-1), B_w1, B_w2)
    x = x + _A_ref(_layernorm(x, axis=-1), A_dft_seq_re, A_dft_seq_im, A_dft_hid_re, A_dft_hid_im)
    x = x + _B_ref(_layernorm(x, axis=-1), B_w1, B_w2)
    return x
```

```cpp
#include <cuda_runtime.h>
#include <cuda_bf16.h>
#include <cuda.h>
#include <stdint.h>

namespace {

constexpr int S_ = 2048, D_ = 576, F_ = 4608;
constexpr int NB = 6;
constexpr int RING_OFF = 9 * 16384;
constexpr int STG_OFF = RING_OFF + NB * 12288;
constexpr int BAR_OFF = STG_OFF + 8192;
constexpr int SMEM_BYTES = BAR_OFF + 512 + 1536 + 1024;
constexpr int T0_OFF = 496;
constexpr int B_FULL = 0, B_EMPTY = NB, B_RFULL = 2 * NB, B_REMPTY = B_RFULL + 9, B_WEMPTY = B_REMPTY + 9, B_SREADY = B_WEMPTY + 9, B_HREADY = B_SREADY + 1, B_SIG = B_HREADY + 1, B_SLAB = B_SIG + 8, B_GUARD = B_SLAB + 6, B_GO = B_GUARD + 1, B_TOTAL = B_GO + 1;
#define CS1_START 6500
#define PF_DELAY 500
#define PF_PACE 520
#define PF1_PACE 400
#define WS_AT 5600
#define BIG_PACE 250
constexpr int WS_EARLY = 3, GO_AT = 12, G2_SKEW = 2;
#define FORCE_FALLBACK 0
constexpr int NSPARE = 2;

constexpr int NOPS = 12;
struct Op { unsigned long long seg; uint32_t meta, post; };
__constant__ Op c_ops[2 * NOPS] = {
  {0x7fffe00876543210ull, 0x7002009u, 0x876u},
  {0xff076543210ull, 0x10004988u, 0x0u},
  {0xe01000000108ull, 0x283u, 0x0u},
  {0x7e00000765432ull, 0x40008246u, 0x1108u},
  {0x7ff81c0432765432ull, 0x27e29259u, 0x432u},
  {0x432765108ull, 0x30004b99u, 0x0u},
  {0x7fffe07432750750ull, 0x7002499u, 0x7432u},
  {0xfe032750618ull, 0x10004d88u, 0x0u},
  {0xe03000000184ull, 0x683u, 0x0u},
  {0x7e00000327506ull, 0x40008646u, 0x4184u},
  {0x7ff81c0506327506ull, 0x27e29659u, 0x6506u},
  {0x506327184ull, 0x30004f99u, 0x0u},
  {0x1feff076543210ull, 0x8004198u, 0x0u},
  {0x7c00ff076543210ull, 0x18007188u, 0x765u},
  {0x1c1001000002108ull, 0x1c0a34u, 0x0u},
  {0x76543ull, 0x40008a65u, 0x6765u},
  {0x432765108ull, 0x28014399u, 0x0u},
  {0xfc0000432765108ull, 0x38007399u, 0x432u},
  {0x1fefe032750618ull, 0x8004598u, 0x0u},
  {0x7c00fe032750618ull, 0x18007588u, 0x327u},
  {0x1c1003000006184ull, 0x1c0e34u, 0x0u},
  {0x32750ull, 0x40008e65u, 0x327u},
  {0x506327184ull, 0x28014799u, 0x0u},
  {0xfc0000506327184ull, 0x38007799u, 0x506u},
};
__constant__ unsigned long long c_stats[4] = {0x876543210ull,0x1765432108ull,0x7432750750ull,0x3327506184ull};
constexpr int NPA = 58, WS_EARLY1 = 4;
__constant__ uint16_t c_pa[NPA] = {8192,8328,8464,8600,8736,8872,9008,9144,9280,2049,2185,2321,2457,2593,2729,2865,3001,19458,10250,10386,43290,10658,10794,60082,11066,11202,2306,2442,2578,11269,18436,2189,2700,2837,2964,43036,10916,11180,59700,10684,10820,2077,2725,2989,2357,2493,18950,3086,10390,43806,10278,10926,60342,10558,10694,2822,2062,2710};
constexpr int NBS = 87;
__constant__ uint8_t c_bs[NBS] = {0,16,32,48,64,80,96,112,128,1,17,33,49,65,81,97,113,5,21,37,53,69,85,101,117,9,25,41,57,73,89,105,121,2,18,34,6,22,38,54,50,66,82,98,114,130,70,86,102,118,134,58,74,90,106,122,138,10,26,42,3,19,35,51,67,83,99,115,131,7,23,39,55,71,87,103,119,135,11,27,43,59,75,91,107,123,139};

__device__ __align__(128) __nv_bfloat16 g_ab[2 * S_ * 2 * D_];
__device__ __align__(128) unsigned long long g_stats[4 * S_];
__device__ __align__(16) float g_csd[2 * D_];
__device__ __align__(16) float g_cs1[F_];
constexpr int FL_X = 0;
constexpr int FL_CP = FL_X + 192;
constexpr int FL_AB = FL_CP + 16;
constexpr int FL_AB0 = FL_AB + 32;
constexpr int FL_XR = FL_AB0 + 64;
constexpr int FL_CSD = FL_XR + 32;
constexpr int FL_CS1 = FL_CSD + 8;
constexpr int FL_DONE = FL_CS1 + 8;
constexpr int FL_TOTAL = FL_DONE + 1;
__device__ __align__(128) unsigned g_flags[FL_TOTAL * 32];
#define FLAG(i) (g_flags + (i) * 32)

struct Params {
  const __nv_bfloat16* x0; const __nv_bfloat16* pwdr; const __nv_bfloat16* pwdi; __nv_bfloat16* out;
  const __nv_bfloat16* pwsr; const __nv_bfloat16* pwsi; const __nv_bfloat16* pw1; const __nv_bfloat16* pw2;
  CUtensorMap xin, wdr, wdi, xw, wsr, wsi, abld, w1, w2, abst, xst, xst8;
};

__device__ __forceinline__ void wgmma_n192_n(float (&d)[96], uint64_t da, uint64_t db, uint32_t keep) {
  asm volatile("{\n.reg .pred p;\nsetp.ne.b32 p, %98, 0;\n"
    "wgmma.mma_async.sync.aligned.m64n192k16.f32.bf16.bf16 {%0, %1, %2, %3, %4, %5, %6, %7, %8, %9, %10, %11, %12, %13, %14, %15, %16, %17, %18, %19, %20, %21, %22, %23, %24, %25, %26, %27, %28, %29, %30, %31, %32, %33, %34, %35, %36, %37, %38, %39, %40, %41, %42, %43, %44, %45, %46, %47, %48, %49, %50, %51, %52, %53, %54, %55, %56, %57, %58, %59, %60, %61, %62, %63, %64, %65, %66, %67, %68, %69, %70, %71, %72, %73, %74, %75, %76, %77, %78, %79, %80, %81, %82, %83, %84, %85, %86, %87, %88, %89, %90, %91, %92, %93, %94, %95}, %96, %97, p, 1, 1, 0, 1;\n}\n"
    : "+f"(d[0]), "+f"(d[1]), "+f"(d[2]), "+f"(d[3]), "+f"(d[4]), "+f"(d[5]), "+f"(d[6]), "+f"(d[7]), "+f"(d[8]), "+f"(d[9]), "+f"(d[10]), "+f"(d[11]), "+f"(d[12]), "+f"(d[13]), "+f"(d[14]), "+f"(d[15]), "+f"(d[16]), "+f"(d[17]), "+f"(d[18]), "+f"(d[19]), "+f"(d[20]), "+f"(d[21]), "+f"(d[22]), "+f"(d[23]), "+f"(d[24]), "+f"(d[25]), "+f"(d[26]), "+f"(d[27]), "+f"(d[28]), "+f"(d[29]), "+f"(d[30]), "+f"(d[31]), "+f"(d[32]), "+f"(d[33]), "+f"(d[34]), "+f"(d[35]), "+f"(d[36]), "+f"(d[37]), "+f"(d[38]), "+f"(d[39]), "+f"(d[40]), "+f"(d[41]), "+f"(d[42]), "+f"(d[43]), "+f"(d[44]), "+f"(d[45]), "+f"(d[46]), "+f"(d[47]), "+f"(d[48]), "+f"(d[49]), "+f"(d[50]), "+f"(d[51]), "+f"(d[52]), "+f"(d[53]), "+f"(d[54]), "+f"(d[55]), "+f"(d[56]), "+f"(d[57]), "+f"(d[58]), "+f"(d[59]), "+f"(d[60]), "+f"(d[61]), "+f"(d[62]), "+f"(d[63]), "+f"(d[64]), "+f"(d[65]), "+f"(d[66]), "+f"(d[67]), "+f"(d[68]), "+f"(d[69]), "+f"(d[70]), "+f"(d[71]), "+f"(d[72]), "+f"(d[73]), "+f"(d[74]), "+f"(d[75]), "+f"(d[76]), "+f"(d[77]), "+f"(d[78]), "+f"(d[79]), "+f"(d[80]), "+f"(d[81]), "+f"(d[82]), "+f"(d[83]), "+f"(d[84]), "+f"(d[85]), "+f"(d[86]), "+f"(d[87]), "+f"(d[88]), "+f"(d[89]), "+f"(d[90]), "+f"(d[91]), "+f"(d[92]), "+f"(d[93]), "+f"(d[94]), "+f"(d[95])
    : "l"(da), "l"(db), "r"(keep));
}
__device__ __forceinline__ void wgmma_n144_k(float (&d)[96], uint64_t da, uint64_t db, uint32_t keep) {
  asm volatile("{\n.reg .pred p;\nsetp.ne.b32 p, %74, 0;\n"
    "wgmma.mma_async.sync.aligned.m64n144k16.f32.bf16.bf16 {%0, %1, %2, %3, %4, %5, %6, %7, %8, %9, %10, %11, %12, %13, %14, %15, %16, %17, %18, %19, %20, %21, %22, %23, %24, %25, %26, %27, %28, %29, %30, %31, %32, %33, %34, %35, %36, %37, %38, %39, %40, %41, %42, %43, %44, %45, %46, %47, %48, %49, %50, %51, %52, %53, %54, %55, %56, %57, %58, %59, %60, %61, %62, %63, %64, %65, %66, %67, %68, %69, %70, %71}, %72, %73, p, 1, 1, 0, 0;\n}\n"
    : "+f"(d[0]), "+f"(d[1]), "+f"(d[2]), "+f"(d[3]), "+f"(d[4]), "+f"(d[5]), "+f"(d[6]), "+f"(d[7]), "+f"(d[8]), "+f"(d[9]), "+f"(d[10]), "+f"(d[11]), "+f"(d[12]), "+f"(d[13]), "+f"(d[14]), "+f"(d[15]), "+f"(d[16]), "+f"(d[17]), "+f"(d[18]), "+f"(d[19]), "+f"(d[20]), "+f"(d[21]), "+f"(d[22]), "+f"(d[23]), "+f"(d[24]), "+f"(d[25]), "+f"(d[26]), "+f"(d[27]), "+f"(d[28]), "+f"(d[29]), "+f"(d[30]), "+f"(d[31]), "+f"(d[32]), "+f"(d[33]), "+f"(d[34]), "+f"(d[35]), "+f"(d[36]), "+f"(d[37]), "+f"(d[38]), "+f"(d[39]), "+f"(d[40]), "+f"(d[41]), "+f"(d[42]), "+f"(d[43]), "+f"(d[44]), "+f"(d[45]), "+f"(d[46]), "+f"(d[47]), "+f"(d[48]), "+f"(d[49]), "+f"(d[50]), "+f"(d[51]), "+f"(d[52]), "+f"(d[53]), "+f"(d[54]), "+f"(d[55]), "+f"(d[56]), "+f"(d[57]), "+f"(d[58]), "+f"(d[59]), "+f"(d[60]), "+f"(d[61]), "+f"(d[62]), "+f"(d[63]), "+f"(d[64]), "+f"(d[65]), "+f"(d[66]), "+f"(d[67]), "+f"(d[68]), "+f"(d[69]), "+f"(d[70]), "+f"(d[71])
    : "l"(da), "l"(db), "r"(keep));
}

__device__ __forceinline__ uint32_t smem_u32(const void* p) { return (uint32_t)__cvta_generic_to_shared(p); }
__device__ __forceinline__ int lane_id() { int l; asm volatile("mov.u32 %0, %%laneid;" : "=r"(l)); return l; }
__device__ __forceinline__ bool elect_one() {
  uint32_t p; asm volatile("{\n.reg .pred p;\nelect.sync _|p, 0xffffffff;\nselp.u32 %0, 1, 0, p;\n}\n" : "=r"(p)); return p;
}
__device__ __forceinline__ uint32_t gtime_lo() { uint32_t t; asm volatile("mov.u32 %0, %%globaltimer_lo;" : "=r"(t)); return t; }
__device__ __forceinline__ void sleep_until(uint32_t tn) {
  int d;
  while ((d = (int)(tn - gtime_lo())) > 0) __nanosleep(d);
}
__device__ __forceinline__ bool expired(uint32_t t0) { uint32_t s; asm volatile("ld.shared.u32 %0, [%1];" : "=r"(s) : "r"(t0)); return gtime_lo() - s > 1000000000u; }
__device__ __forceinline__ void mbar_init(uint32_t bar, uint32_t cnt) { asm volatile("mbarrier.init.shared::cta.b64 [%0], %1;" :: "r"(bar), "r"(cnt) : "memory"); }
__device__ __forceinline__ void mbar_expect_tx(uint32_t bar, uint32_t bytes) { asm volatile("mbarrier.arrive.expect_tx.shared::cta.b64 _, [%0], %1;" :: "r"(bar), "r"(bytes) : "memory"); }
__device__ __forceinline__ void mbar_arrive(uint32_t bar) { asm volatile("mbarrier.arrive.shared::cta.b64 _, [%0];" :: "r"(bar) : "memory"); }
__device__ __forceinline__ bool mbar_try(uint32_t bar, uint32_t parity) {
  uint32_t ok;
  asm volatile("{\n.reg .pred p;\nmbarrier.try_wait.parity.shared::cta.b64 p, [%1], %2;\nselp.u32 %0, 1, 0, p;\n}\n" : "=r"(ok) : "r"(bar), "r"(parity) : "memory");
  return ok;
}
__device__ __forceinline__ void mbar_wait(uint32_t bar, uint32_t parity, uint32_t t0) {
  while (!mbar_try(bar, parity)) { if (expired(t0)) break; }
}
__device__ __forceinline__ unsigned ld_acquire(const unsigned* p) { unsigned v; asm volatile("ld.acquire.gpu.global.u32 %0, [%1];" : "=r"(v) : "l"(p) : "memory"); return v; }
__device__ __forceinline__ void red_release(unsigned* p) { asm volatile("red.release.gpu.global.add.u32 [%0], 1;" :: "l"(p) : "memory"); }
__device__ __forceinline__ void tma_ld2(uint32_t dst, const CUtensorMap* tm, uint32_t bar, int c0, int c1) {
  asm volatile("cp.async.bulk.tensor.2d.shared::cluster.global.mbarrier::complete_tx::bytes [%0], [%1, {%3, %4}], [%2];"
    :: "r"(dst), "l"((uint64_t)tm), "r"(bar), "r"(c0), "r"(c1) : "memory");
}
__device__ __forceinline__ void tma_ld3_mc(uint32_t dst, const CUtensorMap* tm, uint32_t bar, int c0, int c1, int c2) {
  asm volatile("cp.async.bulk.tensor.3d.shared::cluster.global.mbarrier::complete_tx::bytes.multicast::cluster [%0], [%1, {%3, %4, %5}], [%2], %6;"
    :: "r"(dst), "l"((uint64_t)tm), "r"(bar), "r"(c0), "r"(c1), "r"(c2), "h"((uint16_t)3) : "memory");
}
__device__ __forceinline__ void tma_st2(const CUtensorMap* tm, uint32_t src, int c0, int c1) {
  asm volatile("cp.async.bulk.tensor.2d.global.shared::cta.bulk_group [%0, {%2, %3}], [%1];" :: "l"((uint64_t)tm), "r"(src), "r"(c0), "r"(c1) : "memory");
}
__device__ __forceinline__ void tma_red2(const CUtensorMap* tm, uint32_t src, int c0, int c1) {
  asm volatile("cp.reduce.async.bulk.tensor.2d.global.shared::cta.add.bulk_group [%0, {%2, %3}], [%1];" :: "l"((uint64_t)tm), "r"(src), "r"(c0), "r"(c1) : "memory");
}
__device__ __forceinline__ uint32_t touch256(const void* p) { uint32_t v; asm volatile("ld.global.L2::256B.u32 %0, [%1];" : "=r"(v) : "l"(p)); return v; }
__device__ __forceinline__ void bulk_commit() { asm volatile("cp.async.bulk.commit_group;" ::: "memory"); }
template<int N> __device__ __forceinline__ void bulk_wait_read() { asm volatile("cp.async.bulk.wait_group.read %0;" :: "n"(N) : "memory"); }
__device__ __forceinline__ void bulk_wait_all() { asm volatile("cp.async.bulk.wait_group 0;" ::: "memory"); }
__device__ __forceinline__ void fence_async_glb() { asm volatile("fence.proxy.async.global;" ::: "memory"); }
__device__ __forceinline__ unsigned long long ld_relaxed64(const unsigned long long* p) { unsigned long long v; asm volatile("ld.relaxed.gpu.global.u64 %0, [%1];" : "=l"(v) : "l"(p) : "memory"); return v; }
__device__ __forceinline__ void st_relaxed64(unsigned long long* p, unsigned long long v) { asm volatile("st.relaxed.gpu.global.u64 [%0], %1;" :: "l"(p), "l"(v) : "memory"); }
__device__ __forceinline__ void fence_async_smem() { asm volatile("fence.proxy.async.shared::cta;" ::: "memory"); }
__device__ __forceinline__ void wgmma_fence() { asm volatile("wgmma.fence.sync.aligned;" ::: "memory"); }
__device__ __forceinline__ void wgmma_commit() { asm volatile("wgmma.commit_group.sync.aligned;" ::: "memory"); }
template<int N> __device__ __forceinline__ void wgmma_wait() { asm volatile("wgmma.wait_group.sync.aligned %0;" :: "n"(N) : "memory"); }
__device__ __forceinline__ void fence_regs(float (&d)[96]) {
#pragma unroll
  for (int i = 0; i < 96; i++) asm volatile("" : "+f"(d[i]) :: "memory");
}
__device__ __forceinline__ void cluster_sync_all() { asm volatile("barrier.cluster.arrive.relaxed;\nbarrier.cluster.wait;" ::: "memory"); }
__device__ __forceinline__ uint32_t pack_bf16(float lo, float hi) { uint32_t r; asm("cvt.rn.bf16x2.f32 %0, %1, %2;" : "=r"(r) : "f"(hi), "f"(lo)); return r; }
__device__ __forceinline__ uint32_t pack_bf16_relu(float lo, float hi) { uint32_t r; asm("cvt.rn.relu.bf16x2.f32 %0, %1, %2;" : "=r"(r) : "f"(hi), "f"(lo)); return r; }
__device__ __forceinline__ void stsm4(uint32_t addr, uint32_t a, uint32_t b, uint32_t c, uint32_t d) {
  asm volatile("stmatrix.sync.aligned.m8n8.x4.shared.b16 [%0], {%1, %2, %3, %4};" :: "r"(addr), "r"(a), "r"(b), "r"(c), "r"(d) : "memory");
}
__device__ __forceinline__ float2 lds_f2(uint32_t addr) { float2 v; asm volatile("ld.shared.v2.f32 {%0, %1}, [%2];" : "=f"(v.x), "=f"(v.y) : "r"(addr)); return v; }
__device__ __forceinline__ uint4 ldg_cg(const void* p) { uint4 v; asm volatile("ld.global.cg.v4.u32 {%0, %1, %2, %3}, [%4];" : "=r"(v.x), "=r"(v.y), "=r"(v.z), "=r"(v.w) : "l"(p) : "memory"); return v; }
__device__ __forceinline__ float bf_lo(uint32_t w) { return __uint_as_float(w << 16); }
__device__ __forceinline__ float bf_hi(uint32_t w) { return __uint_as_float(w & 0xffff0000u); }
__device__ __forceinline__ float sum8(const uint4& v) {
  return ((bf_lo(v.x) + bf_hi(v.x)) + (bf_lo(v.y) + bf_hi(v.y))) + ((bf_lo(v.z) + bf_hi(v.z)) + (bf_lo(v.w) + bf_hi(v.w)));
}
__device__ __forceinline__ void acc2(uint32_t w, float& s0, float& q0, float& s1, float& q1) {
  const float a = bf_lo(w), b = bf_hi(w);
  s0 += a; s1 += b; q0 = fmaf(a, a, q0); q1 = fmaf(b, b, q1);
}

__device__ __forceinline__ void mbar_arrive_n(uint32_t bar, uint32_t n) { asm volatile("mbarrier.arrive.shared::cta.b64 _, [%0], %1;" :: "r"(bar), "r"(n) : "memory"); }
__device__ __forceinline__ void mbar_expect_tx_cluster(uint32_t bar, uint32_t cta, uint32_t bytes) {
  asm volatile("{\n.reg .b32 ra;\nmapa.shared::cluster.u32 ra, %0, %1;\nmbarrier.arrive.expect_tx.shared::cluster.b64 _, [ra], %2;\n}\n" :: "r"(bar), "r"(cta), "r"(bytes) : "memory");
}
__device__ __forceinline__ void wait_flag(const unsigned* p, unsigned target, uint32_t t0) {
  while (ld_acquire(p) < target) { if (expired(t0)) break; __nanosleep(150); }
}
__device__ __forceinline__ void wait_flag_warp(const unsigned* p, unsigned target, uint32_t t0) {
  while (__any_sync(0xffffffffu, ld_acquire(p) < target && !expired(t0))) {}
}
__device__ __forceinline__ uint4 lds128(uint32_t a) { uint4 v; asm volatile("ld.shared.v4.u32 {%0, %1, %2, %3}, [%4];" : "=r"(v.x), "=r"(v.y), "=r"(v.z), "=r"(v.w) : "r"(a)); return v; }

#define OP_N(m) ((m) & 15)
#define OP_SKIP(m) (((m) >> 4) & 15)
#define OP_TYPE(m) (((m) >> 8) & 3)
#define OP_LAYER(m) (((m) >> 10) & 1)
#define OP_PASS(m) (((m) >> 11) & 3)
#define OP_POST(m) (((m) >> 13) & 7)
#define OP_HWAIT(m) (((m) >> 16) & 1)
#define OP_XREAD(m) (((m) >> 17) & 1)
#define OP_SIG(m) (((m) >> 27) & 7)
#define OP_CONT(m) (((m) >> 30) & 1)
enum { POST_NONE = 0, POST_E1 = 1, POST_SMALL = 2, POST_BIG = 3, POST_H = 4 };

__device__ __forceinline__ uint64_t desc64(uint32_t lo, uint32_t hi) { uint64_t d; asm("mov.b64 %0, {%1, %2};" : "=l"(d) : "r"(lo), "r"(hi)); return d; }
template<bool G1>
__device__ __forceinline__ void mma_k32(float (&acc0)[96], float (&acc1)[96], uint32_t alo, uint32_t alo1, uint32_t blo, uint32_t keep) {
  wgmma_fence();
#pragma unroll
  for (int k = 0; k < 2; k++) {
    const uint64_t da0 = desc64(alo + 2 * k, 0x40000040u), da1 = desc64(alo1 + 2 * k, 0x40000040u);
    if (G1) {
      const uint64_t db = desc64(blo + 2 * k, 0x80000020u);
      wgmma_n144_k(acc0, da0, db, k ? 1 : keep); wgmma_n144_k(acc1, da1, db, k ? 1 : keep);
    } else {
      const uint64_t db = desc64(blo + 128 * k, 0x40000040u);
      wgmma_n192_n(acc0, da0, db, k ? 1 : keep); wgmma_n192_n(acc1, da1, db, k ? 1 : keep);
    }
  }
  wgmma_commit();
}
__device__ __forceinline__ void arrive_at(uint32_t cluster_addr) { asm volatile("mbarrier.arrive.shared::cluster.b64 _, [%0];" :: "r"(cluster_addr) : "memory"); }
__device__ __forceinline__ void mma_half(float (&acc)[96], uint32_t alo, uint32_t blo) {
  wgmma_n192_n(acc, desc64(alo, 0x40000040u), desc64(blo, 0x40000040u), 1);
  wgmma_n192_n(acc, desc64(alo + 2, 0x40000040u), desc64(blo + 128, 0x40000040u), 1);
  wgmma_commit();
}
template<int Q>
__device__ __forceinline__ void stage_slab(const float (&acc)[96], uint32_t d, uint32_t bar) {
#pragma unroll
  for (int jj = 0; jj < 4; jj++) {
    const int j = 4 * (Q * 8 + jj * 2);
    stsm4(d ^ (jj * 32), pack_bf16(acc[j], acc[j + 1]), pack_bf16(acc[j + 2], acc[j + 3]), pack_bf16(acc[j + 4], acc[j + 5]), pack_bf16(acc[j + 6], acc[j + 7]));
  }
  fence_async_smem(); __syncwarp();
  if (elect_one()) mbar_arrive(bar);
}
template<int KIND>
__device__ __forceinline__ void mainloop(float (&acc0)[96], float (&acc1)[96], unsigned long long seg, uint32_t meta, bool signal_next,
                                         int& stage, uint32_t& phase, uint32_t base, int wg, int w4, bool lane0, uint32_t msw, uint32_t post = 0) {
  constexpr bool G1 = KIND == 1;
  const uint32_t bars = base + BAR_OFF, t0 = bars + T0_OFF;
  const uint32_t a0 = ((base & 0x3FFFF) >> 4) | 0x10000u, b0 = (((base + RING_OFF) & 0x3FFFF) >> 4) | (G1 ? 0x10000u : 0x1000000u);
  uint32_t e0, e1;
  asm("mapa.shared::cluster.u32 %0, %1, 0;" : "=r"(e0) : "r"(bars + 8 * B_EMPTY));
  asm("mapa.shared::cluster.u32 %0, %1, 1;" : "=r"(e1) : "r"(bars + 8 * B_EMPTY + 8));
  uint32_t slots = (uint32_t)seg, m = (uint32_t)(seg >> 36), mw = meta >> 18;
  const uint32_t slot8 = (uint32_t)(seg >> 32) << 28;
  int left = OP_N(meta) - (KIND == 2 ? 3 : KIND == 4 ? G2_SKEW : 0);
  uint32_t slot = slots & 15, relb = 0, rela = 0, keep = OP_CONT(meta);
  fence_regs(acc0); fence_regs(acc1);
  do {
    if (KIND < 2 && (m & 512)) mbar_wait(bars + 8 * B_RFULL + 8 * slot, m & 1, t0);
    if (KIND == 0 && left == 3 && OP_HWAIT(meta)) mbar_wait(bars + 8 * B_HREADY, OP_LAYER(meta), t0);
    const uint32_t fb = bars + 8 * stage, alo = a0 + slot * 1024, blo = b0 + stage * 768;
    mbar_wait(fb, phase, t0);
    mma_k32<G1>(acc0, acc1, alo + msw, alo + 512 - msw, blo, keep);
    keep = 1;
    wgmma_wait<1>();
    if (lane0) {
      if (relb) arrive_at(relb);
      if (rela) mbar_arrive_n(rela, G1 ? 1 : 2);
    }
    mbar_wait(fb + 8, phase, t0);
    mma_k32<G1>(acc0, acc1, alo + 4 + msw, alo + 516 - msw, blo + 768, 1);
    left--;
    if (KIND < 2 && left == 0 && signal_next) asm volatile("bar.arrive %0, 256;" :: "r"(2 - wg) : "memory");
    const uint32_t rel0 = e0 + 8 * stage;
    relb = e1 + 8 * stage;
    rela = (m & (1 << 18)) ? bars + 8 * B_REMPTY + 8 * slot + ((mw & 1) ? 72 : 0) : 0;
    slots = (slots >> 4) | slot8; slot = slots & 15; m = (m >> 1) & ~0x20100u; mw >>= 1;
    stage += 2;
    if (stage == NB) { stage = 0; phase ^= 1; }
    wgmma_wait<1>();
    if (lane0) arrive_at(rel0);
  } while (left > 0);
  if (KIND < 2) {
    wgmma_wait<0>();
    fence_regs(acc0); fence_regs(acc1);
    if (lane0) {
      arrive_at(relb);
      if (rela) mbar_arrive_n(rela, G1 ? 1 : 2);
    }
  } else {
    constexpr int D = KIND == 2 ? 3 : G2_SKEW;
    uint32_t st[D], al[D];
#pragma unroll
    for (int j = 0; j < D; j++) {
      st[j] = stage; al[j] = a0 + ((slots >> (4 * j)) & 15) * 1024;
      mbar_wait(bars + 8 * stage, phase, t0);
      wgmma_fence();
      mma_half(acc0, al[j] + msw, b0 + stage * 768);
      if (j == 0) {
        wgmma_wait<1>();
        if (lane0) { arrive_at(relb); if (D == 3) mbar_arrive_n(rela, 2); }
      }
      mbar_wait(bars + 8 * stage + 8, phase, t0);
      wgmma_fence();
      mma_half(acc0, al[j] + 4 + msw, b0 + stage * 768 + 768);
      stage += 2;
      if (stage == NB) { stage = 0; phase ^= 1; }
    }
    const int lane = lane_id();
    const uint32_t off = base + (w4 * 16 + (lane & 15)) * 128 + (((lane >> 4) ^ (lane & 7)) << 4);
    const uint32_t d0 = off + (post & 15) * 16384, d1 = off + ((post >> 4) & 15) * 16384, d2 = off + ((post >> 8) & 15) * 16384;
    mma_half(acc1, al[0] + 512 - msw, b0 + st[0] * 768);
    mma_half(acc1, al[0] + 516 - msw, b0 + st[0] * 768 + 768);
    wgmma_wait<2>();
    fence_regs(acc0);
    asm volatile("bar.sync %0, 128;" :: "r"(3 + wg) : "memory");
    stage_slab<0>(acc0, d0 + (msw << 4), bars + 8 * B_SLAB);
    wgmma_fence();
    mma_half(acc1, al[1] + 512 - msw, b0 + st[1] * 768);
    mma_half(acc1, al[1] + 516 - msw, b0 + st[1] * 768 + 768);
    if (D == 2 && signal_next) asm volatile("bar.arrive %0, 256;" :: "r"(2 - wg) : "memory");
    wgmma_wait<2>();
    if (lane0) { arrive_at(e0 + 8 * st[0]); arrive_at(e1 + 8 * st[0]); }
    stage_slab<1>(acc0, d1 + (msw << 4), bars + 8 * (B_SLAB + 1));
    if (D > 2) {
      wgmma_fence();
      mma_half(acc1, al[2 % D] + 512 - msw, b0 + st[2 % D] * 768);
      mma_half(acc1, al[2 % D] + 516 - msw, b0 + st[2 % D] * 768 + 768);
      if (signal_next) asm volatile("bar.arrive %0, 256;" :: "r"(2 - wg) : "memory");
      wgmma_wait<2>();
    } else wgmma_wait<0>();
    if (lane0) { arrive_at(e0 + 8 * st[1]); arrive_at(e1 + 8 * st[1]); }
    stage_slab<2>(acc0, d2 + (msw << 4), bars + 8 * (B_SLAB + 2));
    wgmma_wait<0>();
    fence_regs(acc1);
    if (D > 2 && lane0) { arrive_at(e0 + 8 * st[2 % D]); arrive_at(e1 + 8 * st[2 % D]); }
    asm volatile("bar.sync %0, 128;" :: "r"(3 + wg) : "memory");
    stage_slab<0>(acc1, d0 + 8192 - (msw << 4), bars + 8 * (B_SLAB + 3));
    stage_slab<1>(acc1, d1 + 8192 - (msw << 4), bars + 8 * (B_SLAB + 4));
    stage_slab<2>(acc1, d2 + 8192 - (msw << 4), bars + 8 * (B_SLAB + 5));
  }
}

__device__ __forceinline__ void load_stats(float2 (&st)[4], uint32_t stg, int w4, int lane, float sgn) {
#pragma unroll
  for (int j = 0; j < 4; j++) {
    st[j] = lds_f2(stg + ((j >> 1) * 64 + w4 * 16 + (lane >> 2) + (j & 1) * 8) * 8);
    if (sgn < 0.f) { st[j].x = -st[j].x; st[j].y = -st[j].y; }
  }
}
__device__ __forceinline__ void publish_stats(unsigned long long* p, float s, float q, bool packed) {
  const float mean = s * (1.f / D_), rstd = rsqrtf(fmaxf(q * (1.f / D_) - mean * mean, 0.f) + 1e-5f);
  const uint32_t lo = packed ? pack_bf16(rstd, rstd) : __float_as_uint(rstd);
  st_relaxed64(p, (unsigned long long)max(lo, 1u) | ((unsigned long long)__float_as_uint(packed ? -mean : -mean * rstd) << 32));
}
__device__ __forceinline__ void load_cs(uint32_t base, const float* src, uint32_t bytes) {
  const uint32_t bar = base + BAR_OFF + 8 * B_SREADY;
  fence_async_glb();
  asm volatile("mbarrier.expect_tx.shared::cta.b64 [%0], %1;" :: "r"(bar), "r"(bytes) : "memory");
  asm volatile("cp.async.bulk.shared::cluster.global.mbarrier::complete_tx::bytes [%0], [%1], %2, [%3];"
               :: "r"(base + STG_OFF + 2560), "l"(src), "r"(bytes), "r"(bar) : "memory");
}

template<int MODE>
__device__ __forceinline__ void cvt_pair(const float (&acc)[96], int j, uint32_t (&r)[4], float2 ca, float2 cb, float2 s0, float2 s1,
                                         uint32_t& chain, uint32_t zero) {
#pragma unroll
  for (int t = 0; t < 2; t++) {
    float v0 = acc[4 * (j + t)], v1 = acc[4 * (j + t) + 1], v2 = acc[4 * (j + t) + 2], v3 = acc[4 * (j + t) + 3];
    const float2 c = t ? cb : ca;
    if (MODE == 2) {
      const float m0 = __uint_as_float(__float_as_uint(s0.y) ^ (chain & zero));
      chain = pack_bf16_relu(fmaf(m0, c.x, v0), fmaf(m0, c.y, v1));
      asm("mul.rn.bf16x2 %0, %1, %2;" : "=r"(r[2 * t]) : "r"(chain), "r"(__float_as_uint(s0.x)));
      const float m1 = __uint_as_float(__float_as_uint(s1.y) ^ (chain & zero));
      chain = pack_bf16_relu(fmaf(m1, c.x, v2), fmaf(m1, c.y, v3));
      asm("mul.rn.bf16x2 %0, %1, %2;" : "=r"(r[2 * t + 1]) : "r"(chain), "r"(__float_as_uint(s1.x)));
    } else {
      if (MODE == 0) {
        v0 = fmaf(s0.y, c.x, v0 * s0.x); v1 = fmaf(s0.y, c.y, v1 * s0.x);
        v2 = fmaf(s1.y, c.x, v2 * s1.x); v3 = fmaf(s1.y, c.y, v3 * s1.x);
      }
      r[2 * t] = pack_bf16(v0, v1); r[2 * t + 1] = pack_bf16(v2, v3);
    }
  }
}
template<int MODE>
__device__ __forceinline__ void epi_ln(const float (&acc0)[96], const float (&acc1)[96], uint32_t post, uint32_t csa, const float2 (&st)[4],
                                       uint32_t base, int w4, int lane, const Params& P, int col, int row, unsigned* flag0) {
  constexpr int PP = MODE == 0 ? 3 : 4, NP = 3 * PP;
  const uint32_t bars = base + BAR_OFF, t0 = bars + T0_OFF;
  const uint32_t off = MODE == 0 ? w4 * 1536 + (lane & 15) * 96 + (lane >> 4) * 16 : (w4 * 16 + (lane & 15)) * 128 + (((lane >> 4) ^ (lane & 7)) << 4);
  float2 c[2 * NP + 4];
#pragma unroll
  for (int i = 0; i < 4; i++) c[i] = lds_f2(csa + i * 32);
  uint32_t sl = 0, chain = 0;
  const uint32_t zero = post >> 31;
#pragma unroll
  for (int p = 0; p < NP; p++) {
    const int q = p / PP, jj = p % PP;
    if (jj == 0) {
      const uint32_t slot = (post >> (4 * q)) & 15;
      mbar_wait(bars + 8 * (B_WEMPTY + slot), (post >> (12 + q)) & 1, t0);
      sl = base + slot * 16384;
    }
    if (p + 2 < NP) { c[2 * p + 4] = lds_f2(csa + (2 * p + 4) * 32); c[2 * p + 5] = lds_f2(csa + (2 * p + 5) * 32); }
    const uint32_t d0 = MODE == 0 ? sl + off + jj * 32 : (sl + off) ^ (jj * 32);
    uint32_t r[4];
    cvt_pair<MODE>(acc0, 2 * p, r, c[2 * p], c[2 * p + 1], st[0], st[1], chain, zero);
    stsm4(d0, r[0], r[1], r[2], r[3]);
    cvt_pair<MODE>(acc1, 2 * p, r, c[2 * p], c[2 * p + 1], st[2], st[3], chain, zero);
    stsm4(d0 + 8192, r[0], r[1], r[2], r[3]);
    if (MODE == 0 && jj == PP - 1) {
      fence_async_smem(); __syncwarp();
      if (elect_one()) {
        tma_st2(&P.abst, sl + w4 * 1536, col + q * 192, row + w4 * 16);
        tma_st2(&P.abst, sl + w4 * 1536 + 8192, col + q * 192, row + 64 + w4 * 16);
        if (q == 0) { bulk_commit(); bulk_wait_all(); red_release(flag0); }
      }
      __syncwarp();
    }
  }
}
__device__ __forceinline__ void flush_small(const float (&acc)[96], int m, uint32_t base, int w4, int lane, const Params& P, int col, int row) {
  const float2 z = make_float2(0.f, 0.f);
  uint32_t dummy = 0;
#pragma unroll
  for (int q = 0; q < 3; q++) {
    uint32_t r[4][4];
#pragma unroll
    for (int jj = 0; jj < 4; jj++) cvt_pair<1>(acc, q * 8 + jj * 2, r[jj], z, z, z, z, dummy, 0);
#pragma unroll
    for (int h = 0; h < 2; h++) {
      if (m + q > 0) { if (elect_one()) bulk_wait_read<1>(); __syncwarp(); }
      const uint32_t buf = base + STG_OFF + w4 * 2048 + h * 1024;
      const uint32_t d = buf + (lane & 7) * 128 + (((lane >> 3) ^ (lane & 7)) << 4);
      stsm4(d, r[0][h], r[0][2 + h], r[1][h], r[1][2 + h]);
      stsm4(d ^ 64, r[2][h], r[2][2 + h], r[3][h], r[3][2 + h]);
      fence_async_smem(); __syncwarp();
      if (elect_one()) { tma_red2(&P.xst8, buf, col + q * 64, row + w4 * 16 + h * 8); bulk_commit(); }
    }
  }
}
__device__ __forceinline__ void store_piece(int u, uint32_t slots, uint32_t parity, uint32_t base, const Params& P, int si, int r) {
  const uint32_t bars = base + BAR_OFF;
  mbar_wait(bars + 8 * (B_SLAB + u), parity, bars + T0_OFF);
  const int h = u >= 3, q = u - 3 * h;
  const uint32_t sl = base + ((slots >> (4 * q)) & 15) * 16384;
  const int row = ((h ^ si) & 1) * 64 + (si & 2) * 16;
  if (elect_one()) {
    tma_red2(&P.xst, sl + row * 128, 384 + q * 64, r * 128 + row);
    tma_red2(&P.xst, sl + (row ^ 32) * 128, 384 + q * 64, r * 128 + (row ^ 32));
  }
  __syncwarp();
}
__device__ __forceinline__ void store_big(uint32_t slots, uint32_t parity, uint32_t base, const Params& P, int si, int r) {
#pragma unroll 1
  for (int u = 0; u < 6; u++) store_piece(u, slots, parity, base, P, si, r);
  if (elect_one()) bulk_commit();
}

__device__ __forceinline__ void cta_ids(int& si, int& r) {
  int b; asm volatile("mov.u32 %0, %%ctaid.x;" : "=r"(b));
  const int cl = b >> 1;
  int role;
  if (cl < 4) role = 2 + cl; else if (cl >= 64) role = cl - 58;
  else if (cl < 36) role = ((cl - 4) & 7) * 8 + ((cl - 4) >> 3);
  else role = (1 + (cl - 36) % 7) * 8 + 4 + (cl - 36) / 7;
  si = role & 7; r = (role >> 3) * 2 + (b & 1);
}
#define IDS int si, r; cta_ids(si, r)

__global__ void __cluster_dims__(2, 1, 1) __launch_bounds__(384, 1) fnet_ffn_kernel(const __grid_constant__ Params P) {
  extern __shared__ uint8_t smem_raw[];
  const uint32_t t_entry = gtime_lo();
  const uint32_t base = __shfl_sync(0xffffffffu, (smem_u32(smem_raw) + 1023) & ~1023u, 0);
  const uint32_t bars = base + BAR_OFF, t0 = bars + T0_OFF;
  const int warp = __shfl_sync(0xffffffffu, threadIdx.x >> 5, 0);
  if (warp < 3 && elect_one()) asm volatile("prefetch.tensormap [%0];" :: "l"((uint64_t)(warp == 0 ? &P.xin : warp == 1 ? &P.wdr : &P.wdi)) : "memory");
  if (blockIdx.x < 2 * NSPARE) {
    const int q = blockIdx.x, t = threadIdx.x;
    if (t == 0) {
      asm volatile("st.shared.u32 [%0], %1;" :: "r"(t0), "r"(t_entry) : "memory");
      mbar_init(bars, 1); mbar_init(bars + 8, 1); mbar_init(bars + 16, 1);
      fence_async_smem();
    }
    __syncthreads();
    const int c = t % 144, hf = t / 144;
    float a[8];
#pragma unroll
    for (int i = 0; i < 8; i++) a[i] = 0.f;
    while (gtime_lo() - t_entry < CS1_START) __nanosleep(200);
#pragma unroll 1
    for (int ch = -3; ch < 18; ch++) {
      const int bf = (ch + 3) % 3;
      if (ch >= 0) {
        mbar_wait(bars + 8 * bf, (ch / 3) & 1, t0);
        if (t < 288) {
#pragma unroll
          for (int i = 0; i < 16; i++) {
            const uint4 y = lds128(base + bf * 73728 + (c >> 3) * 4096 + (hf * 16 + i) * 128 + (((c & 7) ^ (i & 7)) << 4));
            a[0] += bf_lo(y.x); a[1] += bf_hi(y.x); a[2] += bf_lo(y.y); a[3] += bf_hi(y.y);
            a[4] += bf_lo(y.z); a[5] += bf_hi(y.z); a[6] += bf_lo(y.w); a[7] += bf_hi(y.w);
          }
        }
        __syncthreads();
      }
      if (ch + 3 < 18 && (t & 31) == 0 && warp < 6) {
        if (t == 0) mbar_expect_tx(bars + 8 * bf, 73728);
        asm volatile("cp.async.bulk.tensor.3d.shared::cluster.global.mbarrier::complete_tx::bytes [%0], [%1, {%3, %4, %5}], [%2];"
          :: "r"(base + bf * 73728 + warp * 12288), "l"((uint64_t)&P.w1), "r"(bars + 8 * bf), "r"(0), "r"((ch + 3) * 32), "r"(q * 18 + warp * 3) : "memory");
      }
    }
    if (hf == 1) {
      asm volatile("st.shared.v4.f32 [%0], {%1, %2, %3, %4};" :: "r"(base + c * 32), "f"(a[0]), "f"(a[1]), "f"(a[2]), "f"(a[3]) : "memory");
      asm volatile("st.shared.v4.f32 [%0], {%1, %2, %3, %4};" :: "r"(base + c * 32 + 16), "f"(a[4]), "f"(a[5]), "f"(a[6]), "f"(a[7]) : "memory");
    }
    __syncthreads();
    if (hf == 0) {
      const uint4 u = lds128(base + c * 32), v = lds128(base + c * 32 + 16);
      float4* dst = reinterpret_cast<float4*>(g_cs1 + q * 1152 + c * 8);
      dst[0] = make_float4(a[0] + __uint_as_float(u.x), a[1] + __uint_as_float(u.y), a[2] + __uint_as_float(u.z), a[3] + __uint_as_float(u.w));
      dst[1] = make_float4(a[4] + __uint_as_float(v.x), a[5] + __uint_as_float(v.y), a[6] + __uint_as_float(v.z), a[7] + __uint_as_float(v.w));
    }
    __syncthreads();
    if (t == 0) red_release(FLAG(FL_CS1 + q));
    return;
  }
  if (warp >= 8) {
    asm volatile("setmaxnreg.dec.sync.aligned.u32 40;");
    {
      IDS;
      if (elect_one()) {
        if (warp == 8) {
#pragma unroll
          for (int i = 0; i < NB; i++) { mbar_init(bars + 8 * (B_FULL + i), 1); mbar_init(bars + 8 * (B_EMPTY + i), 8); }
        } else if (warp == 9) {
#pragma unroll
          for (int i = 0; i < 9; i++) mbar_init(bars + 8 * (B_RFULL + i), 1);
        } else if (warp == 10) {
#pragma unroll
          for (int i = 0; i < 18; i++) mbar_init(bars + 8 * (B_REMPTY + i), 8);
        } else {
          asm volatile("st.shared.u32 [%0], %1;" :: "r"(t0), "r"(t_entry) : "memory");
          __threadfence_block();
#pragma unroll
          for (int i = B_SREADY; i < B_TOTAL; i++) mbar_init(bars + 8 * i, i == B_SREADY ? 5 : i < B_GUARD ? 4 : 1);
        }
        asm volatile("fence.mbarrier_init.release.cluster;" ::: "memory");
      }
      __syncwarp();
      asm volatile("barrier.cluster.arrive.relaxed;" ::: "memory");
      if (warp == 9) {
        if (elect_one()) {
          fence_async_smem();
#pragma unroll 1
          for (int k = 0; k < 2; k++) {
            tma_ld2(base + k * 16384, &P.xin, bars + 8 * (B_RFULL + k), k * 64, r * 128);
            mbar_expect_tx(bars + 8 * (B_RFULL + k), 16384);
          }
        }
      } else if (warp == 11) {
        const int ln = lane_id();
        unsigned acc = c_ops[ln < 2 * NOPS ? ln : 0].meta + c_pa[ln] + c_pa[NPA - 1] + c_bs[ln] + c_bs[NBS - 1] + (unsigned)c_stats[ln & 3];
        if (acc == 0x12345678u) asm volatile("st.shared.u32 [%0], %1;" :: "r"(t0 + 8), "r"(acc) : "memory");
      }
      __syncwarp();
      asm volatile("barrier.cluster.wait.acquire;" ::: "memory");
      if (warp == 9) {
        __nanosleep(300);
        if (elect_one()) {
#pragma unroll 1
          for (int k = 2; k < 9; k++) {
            tma_ld2(base + k * 16384, &P.xin, bars + 8 * (B_RFULL + k), k * 64, r * 128);
            mbar_expect_tx(bars + 8 * (B_RFULL + k), 16384);
          }
        }
      }
      if (warp == 8 && elect_one()) {
#pragma unroll 1
        for (int k = 0; k < NB / 2; k++) {
          const uint32_t st = 2 * k + (r & 1), fb = bars + 8 * (B_FULL + st);
          tma_ld3_mc(base + RING_OFF + st * 12288, si < 4 ? &P.wdr : &P.wdi, fb, k * 64 + (r & 1) * 32, (si & 3) * 48, 0);
          mbar_expect_tx(fb, 9216);
          mbar_expect_tx_cluster(fb, (r & 1) ^ 1, 9216);
        }
      }
      __syncwarp();
    }
    const int lane = lane_id();
    if (warp == 8) {
      {
        IDS;
        const int rank = r & 1;
        int stage = rank; uint32_t phase = 0, ready = 0;
#pragma unroll 1
        for (int l = 0; l < 2; l++) {
#pragma unroll 1
          for (int j = l ? 0 : NB / 2; j < NBS; j++) {
            const int bs = (l | (j >= 9)) ? c_bs[j] : (j << 4), type = bs & 3, pass = (bs >> 2) & 3, k = bs >> 4;
            const uint32_t fb = bars + 8 * (B_FULL + stage), sb = base + RING_OFF + stage * 12288;
            const uint32_t bytes = type == 0 ? 9216 : 12288;
            const CUtensorMap* tm; int c0 = 0, c1, c2;
            if (type == 0) { tm = si < 4 ? &P.wdr : &P.wdi; c0 = k * 64 + rank * 32; c1 = (si & 3) * 48; c2 = 0; }
            else if (type == 1) { tm = &P.abld; c1 = l * S_ + si * 256 + (k >> 1) * 64 + rank * 32; c2 = (k & 1) * 9 + pass * 3; }
            else if (type == 2) { tm = &P.w1; c1 = k * 64 + rank * 32; c2 = si * 9 + pass * 3; }
            else { tm = &P.w2; c1 = si * 576 + k * 64 + rank * 32; c2 = pass * 3; }
            if (j >= 9 && j < 17) {
              if (j == 9) ready = 0;
              while (!((ready >> ((k >> 2) * 2 + (k & 1))) & 1)) {
                ready = __ballot_sync(0xffffffffu, ld_acquire(FLAG(FL_AB0 + l * 32 + si * 4 + (lane & 3))) >= 16 || expired(t0));
                __syncwarp();
                fence_async_glb();
              }
            }
            if (j == 16 || j == NBS - 20) mbar_wait(bars + 8 * B_GUARD, j != 16, t0);
            mbar_wait(bars + 8 * (B_EMPTY + stage), phase, t0);
            if (elect_one()) {
              tma_ld3_mc(sb, tm, fb, c0, c1, c2);
              mbar_expect_tx(fb, bytes);
              mbar_expect_tx_cluster(fb, rank ^ 1, bytes);
              if (j == GO_AT) mbar_arrive(bars + 8 * B_GO);
            }
            __syncwarp();
            stage += 2;
            if (stage >= NB) { stage -= NB; phase ^= 1; }
          }
        }
      }
    } else if (warp == 9) {
      {
        IDS;
        uint32_t ts; asm volatile("ld.shared.u32 %0, [%1];" : "=r"(ts) : "r"(t0));
#pragma unroll 1
        for (int k = 0; k < WS_EARLY; k++) {
          sleep_until(ts + WS_AT + k * 200);
          __syncwarp();
          mbar_wait(bars + 8 * (B_REMPTY + k), 0, t0);
          if (elect_one()) {
            tma_ld2(base + k * 16384, (k & 1) ? &P.wsi : &P.wsr, bars + 8 * (B_RFULL + k), si * 256 + (k >> 1) * 64, r * 128);
            mbar_expect_tx(bars + 8 * (B_RFULL + k), 16384);
          }
        }
      }
      {
        IDS;
        uint32_t pfb = 0, pph = 0, qfb = 0, qph = 0;
#pragma unroll 1
        for (int j = 9 + WS_EARLY; j < NPA; j++) {
          const uint32_t w = c_pa[j];
          const int kind = w & 3, l = (w >> 2) & 1, idx = (w >> 3) & 15, slot = (w >> 7) & 15, dep = w >> 14;
          if (j == NPA / 2) {
#pragma unroll 1
            for (int t = 0; t < 4; t++) {
              const __nv_bfloat16* q = ((t & 1) ? P.pwsi : P.pwsr) + (size_t)(r * 128 + lane) * S_ + si * 256 + (t >> 1) * 128;
              uint32_t v[4];
#pragma unroll
              for (int u = 0; u < 4; u++) { v[u] = touch256(q + u * 32 * S_); __nanosleep(PF1_PACE); }
              if ((v[0] ^ v[1]) == 0x13579bdfu && (v[2] ^ v[3]) == 0x2468ace0u) asm volatile("st.shared.u32 [%0], %1;" :: "r"(t0 + 8), "r"(v[0]) : "memory");
            }
          }
          if (dep >= 2 && kind == 2) {
            const int v = 2 * l + (kind >> 1);
            const uint32_t slots = (uint32_t)(c_stats[v] >> 24);
            if (dep == 2) {
              bool loaded = false;
#pragma unroll 1
              for (int u = 0; u < 6 || !loaded; u++) {
                if (u < 6) store_piece(u, slots, 0, base, P, si, r);
                if (loaded) __nanosleep(BIG_PACE);
                else if (__all_sync(0xffffffffu, ld_acquire(FLAG(FL_X + (v * 16 + r) * 3 + 1)) >= 8 || expired(t0))) {
                  loaded = true;
                  fence_async_glb();
#pragma unroll 1
                  for (int k = 0; k < 3; k++) {
                    const uint32_t wk = c_pa[j + k], sk = (wk >> 7) & 15;
                    mbar_wait(bars + 8 * (B_REMPTY + sk), (wk >> 13) & 1, t0);
                    if (elect_one()) { tma_ld2(base + sk * 16384, &P.xw, bars + 8 * (B_RFULL + sk), (3 + k) * 64, r * 128); mbar_expect_tx(bars + 8 * (B_RFULL + sk), 16384); }
                    __syncwarp();
                  }
                }
              }
              if (elect_one()) bulk_commit();
              j += 2;
              continue;
            }
            else if (elect_one()) {
              bulk_wait_all();
              red_release(FLAG(FL_X + (v * 16 + r) * 3 + 2));
#pragma unroll
              for (int q = 0; q < 3; q++) mbar_arrive_n(bars + 8 * (B_REMPTY + ((slots >> (4 * q)) & 15)), 8);
            }
          }
          __syncwarp();
          mbar_wait(bars + 8 * (B_REMPTY + slot), (w >> 13) & 1, t0);
          if (dep) { wait_flag_warp(FLAG(FL_X + ((2 * l + (kind >> 1)) * 16 + r) * 3 + dep - 1), 8, t0); fence_async_glb(); }
          const int early = l ? WS_EARLY1 : WS_EARLY;
          if (kind == 1 && idx == early) mbar_wait(bars + 8 * B_GO, l, t0);
          if (kind == 1 && idx >= early + 2) mbar_wait(qfb, qph, t0);
          const uint32_t fb = bars + 8 * (B_RFULL + slot);
          qfb = pfb; qph = pph; pfb = fb; pph = (w >> 13 & 1) ^ 1;
          if (elect_one()) {
            tma_ld2(base + slot * 16384, kind != 1 ? &P.xw : (idx & 1) ? &P.wsi : &P.wsr, fb, kind != 1 ? idx * 64 : si * 256 + (idx >> 1) * 64, r * 128);
            mbar_expect_tx(fb, 16384);
          }
          __syncwarp();
        }
        store_big(c_ops[2 * NOPS - 1].post, 1, base, P, si, r);
        if (elect_one()) bulk_wait_all();
        __syncwarp();
      }
    } else {
      if (warp == 10) {
        IDS;
        if (lane == 0) {
          mbar_arrive_n(bars + 8 * B_SREADY, 4);
#pragma unroll 1
          for (int t = 0; t < 9; t++) mbar_arrive_n(bars + 8 * ((t < 6 ? B_REMPTY : B_WEMPTY) + t), 4);
        }
        uint32_t tn; asm volatile("ld.shared.u32 %0, [%1];" : "=r"(tn) : "r"(t0));
        tn += PF_DELAY;
#pragma unroll 1
        for (int t = 0; t < 2; t++) {
          uint32_t v[8];
#pragma unroll
          for (int u = 0; u < 8; u++) {
            sleep_until(tn);
            const __nv_bfloat16* q = ((u & 4) ? P.pwsi : P.pwsr) + (size_t)(r * 128 + (u & 3) * 32 + lane) * S_ + si * 256 + t * 128;
            v[u] = touch256(q);
            tn += PF_PACE;
          }
          if ((v[0] ^ v[1] ^ v[2] ^ v[3]) == 0x13579bdfu && (v[4] ^ v[5] ^ v[6] ^ v[7]) == 0x2468ace0u) asm volatile("st.shared.u32 [%0], %1;" :: "r"(t0 + 8), "r"(v[0]) : "memory");
        }
      }
#pragma unroll 1
      for (int v = 0; v < 4; v++) {
        IDS;
        if (warp == 11 && v > 1) {
          mbar_wait(bars + 8 * (B_SIG + ((v & 1) ? 2 : 6)), v == 3, t0);
          if (lane == 0) load_cs(base, (v & 1) ? g_cs1 + si * 576 : g_csd + si * 144, (v & 1) ? 2304 : 576);
        }
        if (warp == 11 && v == 1) mbar_wait(bars + 8 * (B_SIG + 2), 0, t0);
        if (v == 2) {
          if (warp == 11 && lane == 0) mbar_arrive(bars + 8 * B_SREADY);
        } else if (v > 0 || warp == 11) {
        const unsigned long long sj = c_stats[v];
        uint32_t slots = (uint32_t)sj, m = (uint32_t)(sj >> 36);
        const int row = si * 16 + (warp - 10) * 8 + (lane >> 2);
        const uint32_t slot8 = (uint32_t)(sj >> 32) << 28, a0 = base + row * 128 + (lane & 3) * 32;
        float s = 0.f, q = 0.f, s1 = 0.f, q1 = 0.f;
#pragma unroll 1
        for (int t = v ? 0 : 9; t < 9; t++) {
          const uint32_t slot = slots & 15;
          {
            mbar_wait(bars + 8 * (B_RFULL + slot), m & 1, t0);
            const uint32_t a = (a0 + slot * 16384) ^ ((lane & 4) << 2);
            const uint4 x = lds128(a), y = lds128(a ^ 16);
            acc2(x.x, s, q, s1, q1); acc2(x.y, s, q, s1, q1); acc2(x.z, s, q, s1, q1); acc2(x.w, s, q, s1, q1);
            acc2(y.x, s, q, s1, q1); acc2(y.y, s, q, s1, q1); acc2(y.z, s, q, s1, q1); acc2(y.w, s, q, s1, q1);
          }
          slots = (slots >> 4) | slot8; m >>= 1;
        }
        s += s1; q += q1;
        s += __shfl_xor_sync(0xffffffffu, s, 1); q += __shfl_xor_sync(0xffffffffu, q, 1);
        s += __shfl_xor_sync(0xffffffffu, s, 2); q += __shfl_xor_sync(0xffffffffu, q, 2);
        unsigned long long* gs = g_stats + v * S_ + r * 128;
        if ((lane & 3) == 0 && v > 0) {
          publish_stats(gs + row, s, q, v & 1);
          st_relaxed64(gs + row - S_, 0ull);
        }
        if (warp == 11 && v < 2 && lane == 0) {
          wait_flag(v ? FLAG(FL_CS1 + (si >> 1)) : FLAG(FL_CSD + si), v ? 1 : 16, t0);
          load_cs(base, v ? g_cs1 + si * 576 : g_csd + si * 144, v ? 2304 : 576);
        }
        __syncwarp();
#pragma unroll 1
        for (int g0 = (v ? (warp - 10) * 64 : 0) + lane; g0 < (warp - 9) * 64; g0 += 64) {
          unsigned long long u0, u1;
          do { u0 = ld_relaxed64(gs + g0); u1 = ld_relaxed64(gs + g0 + 32); } while (((uint32_t)u0 == 0 || (uint32_t)u1 == 0) && !expired(t0));
          asm volatile("st.shared.u64 [%0], %1;\nst.shared.u64 [%0+256], %2;" :: "r"(base + STG_OFF + g0 * 8), "l"(u0), "l"(u1) : "memory");
        }
        __syncwarp();
        if (lane == 0) mbar_arrive_n(bars + 8 * B_SREADY, warp == 10 ? 4 : 1);
        }
        if (warp == 10) {
          {
#pragma unroll 1
            for (int j = (v & 1) * 4; j < (v == 3 ? 5 : (v & 1) * 5 + 3); j++) {
              const int l = v >> 1;
              if (j == 7) {
                const uint32_t slots = (uint32_t)(c_stats[2] >> 24);
                store_big(slots, 1, base, P, si, r);
                if (elect_one()) {
                  bulk_wait_all();
#pragma unroll
                  for (int q = 0; q < 3; q++) mbar_arrive_n(bars + 8 * (B_REMPTY + ((slots >> (4 * q)) & 15)), 8);
                }
              } else mbar_wait(bars + 8 * (B_SIG + j), l, t0);
              unsigned* f = j == 0 ? FLAG(FL_AB + l * 16 + r) : j == 4 ? FLAG(FL_XR + l * 16 + r) : FLAG(FL_X + ((v + 1) * 16 + r) * 3 + (j & 3) - 1);
              if (elect_one()) red_release(f);
              __syncwarp();
              if (j == 4) {
                while (__any_sync(0xffffffffu, ld_acquire(f) < 8 && !expired(t0))) __nanosleep(100);
                if (elect_one()) mbar_arrive(bars + 8 * B_GUARD);
                __syncwarp();
              }
            }
          }
          __syncwarp();
        } else {
         if (v == 0 && lane < 12) asm volatile("prefetch.tensormap [%0];" :: "l"((uint64_t)(&P.xin + lane)) : "memory");
         if (!(v & 1)) {
          const int l = v >> 1;
          mbar_wait(bars + 8 * B_SIG, l, t0);
          const unsigned* f = lane < 2 ? FLAG(FL_AB + l * 16 + 2 * si + lane) : l ? FLAG(FL_AB + 16 + r) : FLAG(FL_CP + r);
          while (!__all_sync(0xffffffffu, ld_acquire(f) >= 8)) { if (__any_sync(0xffffffffu, expired(t0))) break; __nanosleep(100); }
          __syncwarp();
          fence_async_glb();
          if (lane == 0) mbar_arrive(bars + 8 * B_GUARD);
          __syncwarp();
         }
        }
      }
      unsigned last = 0;
      if (lane == 0) { __threadfence(); last = atomicAdd(FLAG(FL_DONE), 1u) == 2 * 128 - 1; }
      if (__shfl_sync(0xffffffffu, last, 0)) {
        __threadfence();
        for (int i = lane; i < FL_TOTAL; i += 32) *FLAG(i) = 0;
        for (int i = lane; i < S_ / 2; i += 32) reinterpret_cast<uint4*>(g_stats + 3 * S_)[i] = make_uint4(0, 0, 0, 0);
      }
    }
    __syncwarp();
    cluster_sync_all();
  } else {
    asm volatile("barrier.cluster.arrive.relaxed;" ::: "memory");
    if (warp >= 4) {
    IDS;

    const int t = threadIdx.x - 128;
    const size_t o = (size_t)(r * 128 + si * 16 + (t >> 3)) * D_ + (t & 7) * 8;
    const int jc = r * 9 + min(t >> 3, 8);
    const __nv_bfloat16* wd = (si < 4 ? P.pwdr : P.pwdi) + ((jc / 48) * 192 + (si & 3) * 48 + jc % 48) * D_ + (t & 7) * 8;
    uint4 x[9], y[9];
#pragma unroll
    for (int i = 0; i < 9; i++) y[i] = ldg_cg(wd + i * 64);
#pragma unroll
    for (int i = 0; i < 9; i++) x[i] = ldg_cg(P.x0 + o + i * 64);
    float sum = 0.f;
#pragma unroll
    for (int i = 0; i < 9; i++) sum += sum8(y[i]);
    sum += __shfl_xor_sync(0xffffffffu, sum, 1); sum += __shfl_xor_sync(0xffffffffu, sum, 2); sum += __shfl_xor_sync(0xffffffffu, sum, 4);
    if (t < 72 && (t & 7) == 0) g_csd[si * 144 + r * 9 + (t >> 3)] = sum;
    asm volatile("bar.sync 4, 128;" ::: "memory");
    if (t == 96) { red_release(FLAG(FL_CSD + si)); }
    __syncwarp();
    {
      float s = 0.f, q = 0.f, s1 = 0.f, q1 = 0.f;
#pragma unroll
      for (int i = 0; i < 9; i++) { acc2(x[i].x, s, q, s1, q1); acc2(x[i].y, s, q, s1, q1); acc2(x[i].z, s, q, s1, q1); acc2(x[i].w, s, q, s1, q1); }
      s += s1; q += q1;
#pragma unroll
      for (int m = 1; m < 8; m <<= 1) { s += __shfl_xor_sync(0xffffffffu, s, m); q += __shfl_xor_sync(0xffffffffu, q, m); }
      if ((t & 7) == 0) publish_stats(g_stats + r * 128 + si * 16 + (t >> 3), s, q, false);
    }
#pragma unroll
    for (int i = 0; i < 9; i++) *reinterpret_cast<uint4*>(P.out + o + i * 64) = x[i];
    fence_async_glb();
    asm volatile("bar.sync 4, 128;" ::: "memory");
    if (t == 0) red_release(FLAG(FL_CP + r));
    }
    if (warp < 4 && c_ops[0].post == 0x12345678u) asm volatile("st.shared.u32 [%0], %1;" :: "r"(t0 + 8), "r"(0) : "memory");
    __syncwarp();
    asm volatile("setmaxnreg.inc.sync.aligned.u32 232;");
    asm volatile("barrier.cluster.wait.acquire;" ::: "memory");
    const int lane = lane_id();
    const int wg = warp >> 2, w4 = warp & 3;
    uint32_t msw;
    { IDS; msw = (si & 1) * 512; }
    float acc0[96], acc1[96];
#pragma unroll
    for (int j = 0; j < 96; j++) { asm volatile("" : "=f"(acc0[j])); asm volatile("" : "=f"(acc1[j])); }
    int stage = 0; uint32_t phase = 0;
#pragma unroll 1
    for (int i = 0; i < NOPS; i++) {
      const Op& op = c_ops[wg * NOPS + i];
      const uint32_t meta = op.meta;
      const int l = OP_LAYER(meta);
      const uint32_t stg = base + STG_OFF;
      stage += 2 * OP_SKIP(meta);
      while (stage >= NB) { stage -= NB; phase ^= 1; }
      if (i + wg > 0) asm volatile("bar.sync %0, 256;" :: "r"(1 + wg) : "memory");
      const bool signal_next = i + wg < NOPS;
      const uint32_t post = op.post;
      if (OP_TYPE(meta) == 0) {
        IDS;
        mainloop<1>(acc0, acc1, op.seg, meta, signal_next, stage, phase, base, wg, w4, lane == 0, 0);
        const int lane = lane_id();
        mbar_wait(bars + 8 * B_SREADY, 0, t0);
        float2 st[4];
        load_stats(st, stg, w4, lane, si < 4 ? 1.f : -1.f);
        epi_ln<0>(acc0, acc1, post, stg + 2560 + (lane & 3) * 8, st, base, w4, lane, P, (si >> 2) * D_ + (si & 3) * 48, l * S_ + r * 128, FLAG(FL_AB0 + l * 32 + r * 2 + (si >> 2)));
        if (elect_one()) {
          bulk_commit(); bulk_wait_all();
          mbar_arrive(bars + 8 * B_SIG);
#pragma unroll
          for (int q = 0; q < 3; q++) mbar_arrive_n(bars + 8 * (B_REMPTY + ((post >> (4 * q)) & 15)), 2);
        }
        __syncwarp();
#pragma unroll
        for (int j = 72; j < 96; j++) acc1[j] = 0.f;
      } else if (OP_POST(meta) == POST_BIG) {
        if (OP_TYPE(meta) == 1) mainloop<4>(acc0, acc1, op.seg, meta, signal_next, stage, phase, base, wg, w4, lane == 0, msw, post);
        else mainloop<2>(acc0, acc1, op.seg, meta, signal_next, stage, phase, base, wg, w4, lane == 0, msw, post);
            if (i == NOPS / 2 - 1) {
              IDS;
              const int tid = w4 * 32 + lane_id(), row = si * 16 + (tid >> 3);
              const unsigned long long sj = c_stats[2];
              uint32_t slots = (uint32_t)sj, m = (uint32_t)(sj >> 36);
              float s = 0.f, q = 0.f, s1 = 0.f, q1 = 0.f;
#pragma unroll 1
              for (int t = 0; t < 9; t++) {
                const uint32_t slot = slots & 15;
                if (t < 6) {
                  mbar_wait(bars + 8 * (B_RFULL + slot), m & 1, t0);
                  const uint4 x = lds128(base + slot * 16384 + row * 128 + (tid & 7) * 16);
                  acc2(x.x, s, q, s1, q1); acc2(x.y, s, q, s1, q1); acc2(x.z, s, q, s1, q1); acc2(x.w, s, q, s1, q1);
                }
                __syncwarp();
                if (lane == 0) mbar_arrive(bars + 8 * ((t < 6 ? B_REMPTY : B_WEMPTY) + slot));
                slots = (slots >> 4) | ((uint32_t)(sj >> 32) << 28); m >>= 1;
              }
              {
                wait_flag_warp(FLAG(FL_X + (32 + r) * 3 + 2), 8, t0);
                const __nv_bfloat16* src = P.out + (size_t)(r * 128 + row) * D_ + 384 + (tid & 7) * 8;
                const uint4 x = ldg_cg(src), y = ldg_cg(src + 64), z = ldg_cg(src + 128);
                acc2(x.x, s, q, s1, q1); acc2(x.y, s, q, s1, q1); acc2(x.z, s, q, s1, q1); acc2(x.w, s, q, s1, q1);
                acc2(y.x, s, q, s1, q1); acc2(y.y, s, q, s1, q1); acc2(y.z, s, q, s1, q1); acc2(y.w, s, q, s1, q1);
                acc2(z.x, s, q, s1, q1); acc2(z.y, s, q, s1, q1); acc2(z.z, s, q, s1, q1); acc2(z.w, s, q, s1, q1);
              }
              s += s1; q += q1;
#pragma unroll
              for (int o = 1; o < 8; o <<= 1) { s += __shfl_xor_sync(0xffffffffu, s, o); q += __shfl_xor_sync(0xffffffffu, q, o); }
              unsigned long long* gs = g_stats + 2 * S_ + r * 128;
              if ((tid & 7) == 0) { publish_stats(gs + row, s, q, false); st_relaxed64(gs + row - S_, 0ull); }
              unsigned long long u;
              do { u = ld_relaxed64(gs + tid); } while (__any_sync(0xffffffffu, (uint32_t)u == 0 && !expired(t0)));
              asm volatile("st.shared.u64 [%0], %1;" :: "r"(stg + tid * 8), "l"(u) : "memory");
              __syncwarp();
              if (lane == 0) mbar_arrive(bars + 8 * B_SREADY);
            }
      } else {
        mainloop<0>(acc0, acc1, op.seg, meta, signal_next, stage, phase, base, wg, w4, lane == 0, (OP_TYPE(meta) & 1) ? msw : 0);
        const int pk = OP_POST(meta);
        if (pk == POST_H) {
          const int lane = lane_id();
          if (OP_XREAD(meta) && lane == 0) mbar_arrive(bars + 8 * (B_SIG + 4));
          mbar_wait(bars + 8 * B_SREADY, 1, t0);
          float2 st[4];
          load_stats(st, stg, w4, lane, 1.f);
          epi_ln<2>(acc0, acc1, post, stg + 2560 + OP_PASS(meta) * 768 + (lane & 3) * 8, st, base, w4, lane, P, 0, 0, nullptr);
          fence_async_smem(); __syncwarp();
          if (OP_XREAD(meta) && lane == 0) mbar_arrive(bars + 8 * B_HREADY);
        } else if (pk != POST_NONE) {
          {
            IDS;
            if (wg == 0) mbar_wait(bars + 8 * (B_SIG + OP_SIG(meta) - 1), l, t0);
            const int lane = lane_id();
            flush_small(acc0, 0, base, w4, lane, P, OP_PASS(meta) * 192, r * 128 + (msw >> 3));
            flush_small(acc1, 1, base, w4, lane, P, OP_PASS(meta) * 192, r * 128 + 64 - (msw >> 3));
            if (elect_one()) { bulk_wait_all(); mbar_arrive(bars + 8 * (B_SIG + OP_SIG(meta))); }
            __syncwarp();
          }
        }
      }
    }
    cluster_sync_all();
  }
}

__device__ __nv_bfloat16 g_fb_xn[S_ * D_];
__device__ __nv_bfloat16 g_fb_h[S_ * F_];
__global__ void fb_ln(const __nv_bfloat16* x, __nv_bfloat16* copy) {
  const int row = blockIdx.x * 8 + (threadIdx.x >> 5), lane = threadIdx.x & 31;
  float v[18], s = 0.f, q = 0.f;
  for (int i = 0; i < 18; i++) { v[i] = __bfloat162float(x[row * D_ + i * 32 + lane]); s += v[i]; }
  for (int o = 16; o; o >>= 1) s += __shfl_xor_sync(0xffffffffu, s, o);
  const float mean = s * (1.f / D_);
  for (int i = 0; i < 18; i++) q += (v[i] - mean) * (v[i] - mean);
  for (int o = 16; o; o >>= 1) q += __shfl_xor_sync(0xffffffffu, q, o);
  const float rstd = rsqrtf(q * (1.f / D_) + 1e-5f);
  for (int i = 0; i < 18; i++) {
    g_fb_xn[row * D_ + i * 32 + lane] = __float2bfloat16((v[i] - mean) * rstd);
    if (copy) copy[row * D_ + i * 32 + lane] = __float2bfloat16(v[i]);
  }
}
__global__ void fb_gemm(const __nv_bfloat16* A, int lda, const __nv_bfloat16* B, int sk, int sn, __nv_bfloat16* C, int ldc, int K, int mode) {
  __shared__ float As[16][65], Bs[16][65];
  const int t = threadIdx.x, tx = t & 15, ty = t >> 4, m0 = blockIdx.y * 64, n0 = blockIdx.x * 64;
  float acc[4][4] = {};
  for (int k0 = 0; k0 < K; k0 += 16) {
    for (int i = t; i < 1024; i += 256) {
      As[i & 15][i >> 4] = __bfloat162float(A[(size_t)(m0 + (i >> 4)) * lda + k0 + (i & 15)]);
      const int kk = sn == 1 ? i >> 6 : i & 15, nn = sn == 1 ? i & 63 : i >> 4;
      Bs[kk][nn] = __bfloat162float(B[(size_t)(k0 + kk) * sk + (size_t)(n0 + nn) * sn]);
    }
    __syncthreads();
    for (int k = 0; k < 16; k++)
      for (int i = 0; i < 4; i++)
        for (int j = 0; j < 4; j++) acc[i][j] = fmaf(As[k][ty * 4 + i], Bs[k][tx + 16 * j], acc[i][j]);
    __syncthreads();
  }
  for (int i = 0; i < 4; i++)
    for (int j = 0; j < 4; j++) {
      __nv_bfloat16* c = C + (size_t)(m0 + ty * 4 + i) * ldc + n0 + tx + 16 * j;
      const float v = acc[i][j];
      *c = __float2bfloat16(mode == 0 ? v : mode == 1 ? fmaxf(v, 0.f) : mode == 2 ? __bfloat162float(*c) + v : __bfloat162float(*c) - v);
    }
}

typedef CUresult (*PFN_encodeTiled)(CUtensorMap*, CUtensorMapDataType, cuuint32_t, void*, const cuuint64_t*, const cuuint64_t*,
                                    const cuuint32_t*, const cuuint32_t*, CUtensorMapInterleave, CUtensorMapSwizzle,
                                    CUtensorMapL2promotion, CUtensorMapFloatOOBfill);

void map2(PFN_encodeTiled enc, CUtensorMap* m, const void* ptr, uint64_t cols, uint64_t rows, uint32_t b0, uint32_t b1, CUtensorMapSwizzle sw) {
  cuuint64_t dims[2] = {cols, rows}; cuuint64_t str[1] = {cols * 2}; cuuint32_t box[2] = {b0, b1}; cuuint32_t es[2] = {1, 1};
  enc(m, CU_TENSOR_MAP_DATA_TYPE_BFLOAT16, 2, const_cast<void*>(ptr), dims, str, box, es, CU_TENSOR_MAP_INTERLEAVE_NONE, sw,
      CU_TENSOR_MAP_L2_PROMOTION_NONE, CU_TENSOR_MAP_FLOAT_OOB_FILL_NONE);
}
void map3(PFN_encodeTiled enc, CUtensorMap* m, const void* ptr, uint64_t cols, uint64_t rows) {
  cuuint64_t dims[3] = {64, rows, cols / 64}; cuuint64_t str[2] = {cols * 2, 128}; cuuint32_t box[3] = {64, 32, 3}; cuuint32_t es[3] = {1, 1, 1};
  enc(m, CU_TENSOR_MAP_DATA_TYPE_BFLOAT16, 3, const_cast<void*>(ptr), dims, str, box, es, CU_TENSOR_MAP_INTERLEAVE_NONE,
      CU_TENSOR_MAP_SWIZZLE_128B, CU_TENSOR_MAP_L2_PROMOTION_NONE, CU_TENSOR_MAP_FLOAT_OOB_FILL_NONE);
}

}

extern "C" void kernel_launch(void* const* d_in, const int* in_sizes, int n_in, void* d_out, int out_size) {
  (void)in_sizes; (void)n_in; (void)out_size;
  static Params P;
  static const void* cached[9] = {nullptr};
  static bool fused = false;
  static void *xn, *hbuf, *ab;
  bool same = cached[8] == d_out;
  for (int i = 0; i < 8; i++) same = same && cached[i] == d_in[i];
  if (!same) {
    void* fn = nullptr; cudaDriverEntryPointQueryResult qr;
    cudaGetDriverEntryPoint("cuTensorMapEncodeTiled", &fn, cudaEnableDefault, &qr);
    PFN_encodeTiled enc = (PFN_encodeTiled)fn;
    cudaGetSymbolAddress(&ab, g_ab); cudaGetSymbolAddress(&xn, g_fb_xn); cudaGetSymbolAddress(&hbuf, g_fb_h);
    const CUtensorMapSwizzle SW = CU_TENSOR_MAP_SWIZZLE_128B;
    map2(enc, &P.xin, d_in[0], D_, S_, 64, 128, SW);
    map2(enc, &P.xw, d_out, D_, S_, 64, 128, SW);
    map2(enc, &P.wsr, d_in[1], S_, S_, 64, 128, SW);
    map2(enc, &P.wsi, d_in[2], S_, S_, 64, 128, SW);
    for (int i = 0; i < 2; i++) {
      cuuint64_t dims[3] = {D_, 192, 3}; cuuint64_t str[2] = {D_ * 2, 192 * D_ * 2}; cuuint32_t box[3] = {32, 48, 3}; cuuint32_t es[3] = {1, 1, 1};
      enc(i ? &P.wdi : &P.wdr, CU_TENSOR_MAP_DATA_TYPE_BFLOAT16, 3, d_in[3 + i], dims, str, box, es, CU_TENSOR_MAP_INTERLEAVE_NONE,
          CU_TENSOR_MAP_SWIZZLE_64B, CU_TENSOR_MAP_L2_PROMOTION_L2_128B, CU_TENSOR_MAP_FLOAT_OOB_FILL_NONE);
    }
    map3(enc, &P.abld, ab, 2 * D_, 2 * S_);
    map3(enc, &P.w1, d_in[6], F_, D_);
    map3(enc, &P.w2, d_in[7], D_, F_);
    map2(enc, &P.abst, ab, 2 * D_, 2 * S_, 48, 16, CU_TENSOR_MAP_SWIZZLE_NONE);
    map2(enc, &P.xst, d_out, D_, S_, 64, 32, SW);
    map2(enc, &P.xst8, d_out, D_, S_, 64, 8, SW);
    P.x0 = (const __nv_bfloat16*)d_in[0]; P.pwsr = (const __nv_bfloat16*)d_in[1]; P.pwsi = (const __nv_bfloat16*)d_in[2];
    P.pwdr = (const __nv_bfloat16*)d_in[3]; P.pwdi = (const __nv_bfloat16*)d_in[4];
    P.pw1 = (const __nv_bfloat16*)d_in[6]; P.pw2 = (const __nv_bfloat16*)d_in[7]; P.out = (__nv_bfloat16*)d_out;
    cudaFuncSetAttribute(fnet_ffn_kernel, cudaFuncAttributeMaxDynamicSharedMemorySize, SMEM_BYTES);
    cudaLaunchConfig_t cfg = {};
    cfg.gridDim = dim3((64 + NSPARE) * 2); cfg.blockDim = dim3(384); cfg.dynamicSmemBytes = SMEM_BYTES;
    cudaLaunchAttribute at; at.id = cudaLaunchAttributeClusterDimension; at.val.clusterDim.x = 2; at.val.clusterDim.y = 1; at.val.clusterDim.z = 1;
    cfg.attrs = &at; cfg.numAttrs = 1;
    int ncl = 0;
    fused = cudaOccupancyMaxActiveClusters(&ncl, fnet_ffn_kernel, &cfg) == cudaSuccess && ncl >= 64 + FORCE_FALLBACK;
    (void)cudaGetLastError();
    for (int i = 0; i < 8; i++) cached[i] = d_in[i];
    cached[8] = d_out;
  }
  if (fused) {
    fnet_ffn_kernel<<<(64 + NSPARE) * 2, 384, SMEM_BYTES>>>(P);
    return;
  }
  typedef __nv_bfloat16 bf;
  bf *a = (bf*)ab, *b = a + S_ * D_;
  for (int l = 0; l < 2; l++) {
    fb_ln<<<S_ / 8, 256>>>(l ? P.out : P.x0, l ? nullptr : P.out);
    fb_gemm<<<dim3(D_ / 64, S_ / 64), 256>>>((bf*)xn, D_, P.pwdr, 1, D_, a, D_, D_, 0);
    fb_gemm<<<dim3(D_ / 64, S_ / 64), 256>>>((bf*)xn, D_, P.pwdi, 1, D_, b, D_, D_, 0);
    fb_gemm<<<dim3(D_ / 64, S_ / 64), 256>>>(P.pwsr, S_, a, D_, 1, P.out, D_, S_, 2);
    fb_gemm<<<dim3(D_ / 64, S_ / 64), 256>>>(P.pwsi, S_, b, D_, 1, P.out, D_, S_, 3);
    fb_ln<<<S_ / 8, 256>>>(P.out, nullptr);
    fb_gemm<<<dim3(F_ / 64, S_ / 64), 256>>>((bf*)xn, D_, P.pw1, F_, 1, (bf*)hbuf, F_, D_, 1);
    fb_gemm<<<dim3(D_ / 64, S_ / 64), 256>>>((bf*)hbuf, F_, P.pw2, D_, 1, P.out, D_, F_, 2);
  }
}
```
